```python
import torch

def _softmax(x, axis=-1):
    return torch.softmax(x, dim=axis)

def _gelu(x):
    return torch.nn.functional.gelu(x, approximate='tanh')

def _silu(x):
    return torch.nn.functional.silu(x)

def _sigmoid(x):
    return torch.sigmoid(x)

def _layernorm(x, axis=-1, eps=1e-05):
    m = x.mean(dim=axis, keepdim=True)
    v = x.var(dim=axis, keepdim=True, unbiased=False)
    return (x - m) / torch.sqrt(v + eps)

def _scatter_add(tgt, idx, src, axis=0):
    return tgt.clone().index_add_(axis, idx, src)

def _segment_sum(src, seg, n):
    out = torch.zeros((n,) + src.shape[1:], dtype=src.dtype)
    return out.index_add_(0, seg, src)

def _pad(x, pw):
    flat = tuple((v for pair in reversed(pw) for v in pair))
    return torch.nn.functional.pad(x, flat)
kernel_name = 'gated_mix__linear_kernel_hedgehog__mixer_gmlp__prompt'

def setup_inputs():

    _w = lambda a: (lambda t: t.to(torch.bfloat16) if t.is_floating_point() else t)(torch.as_tensor(a))

    def _A_setup():
        B, S, D, H = (1, 2048, 448, 16)
        Dh = D // H
        return {'x': _w((lambda *s: torch.randn(*s, dtype=torch.bfloat16) * 0.05)(B, S, D)), 'wqkv': _w((lambda *s: torch.randn(*s, dtype=torch.bfloat16) * 1.6)(D, 3 * D)), 'w_phi': _w((lambda *s: torch.randn(*s, dtype=torch.bfloat16) * 1.6)(H, Dh, Dh) * Dh ** (-0.5)), 'wo': _w((lambda *s: torch.randn(*s, dtype=torch.bfloat16) * 0.1)(D, D))}
    _A_in = _A_setup()

    def _B_setup():
        B, S, D, F = (1, 2048, 448, 1792)
        Fh = F // 2
        return {'x': _w((lambda *s: torch.randn(*s, dtype=torch.bfloat16) * 0.05)(B, S, D)), 'w_in': _w((lambda *s: torch.randn(*s, dtype=torch.bfloat16) * 0.4)(D, 2 * Fh)), 'w_sp': _w(0.01 * (lambda *s: torch.randn(*s, dtype=torch.bfloat16) * 0.4)(S, S)), 'b_sp': _w(1.0 + 0.01 * (lambda *s: torch.randn(*s, dtype=torch.bfloat16) * 0.05)(S)), 'w_out': _w((lambda *s: torch.randn(*s, dtype=torch.bfloat16) * 0.05)(Fh, D))}
    _B_in = _B_setup()
    return {'A_x': _A_in['x'], 'A_wqkv': _A_in['wqkv'], 'A_w_phi': _A_in['w_phi'], 'A_wo': _A_in['wo'], 'B_x': _B_in['x'], 'B_w_in': _B_in['w_in'], 'B_w_sp': _B_in['w_sp'], 'B_b_sp': _B_in['b_sp'], 'B_w_out': _B_in['w_out'], 'gate_w': _w((lambda *s: torch.randn(*s, dtype=torch.bfloat16) * 0.05)(448) * 16.0)}

def reference(A_x, A_wqkv, A_w_phi, A_wo, B_x, B_w_in, B_w_sp, B_b_sp, B_w_out, gate_w):

    def _A_ref(x, wqkv, w_phi, wo):
        B, S, D = x.shape
        H = 16
        Dh = D // H
        qkv = (lambda x, *d: x.permute(*d))((x @ wqkv).reshape(B, S, 3, H, Dh), 2, 0, 3, 1, 4)
        q, k, v = (qkv[0], qkv[1], qkv[2])
        pq = torch.einsum('bhsd,hdf->bhsf', q, w_phi)
        pk = torch.einsum('bhsd,hdf->bhsf', k, w_phi)
        phi_q = torch.concatenate([_softmax(pq, axis=-1), _softmax(-pq, axis=-1)], axis=-1)
        phi_k = torch.concatenate([_softmax(pk, axis=-1), _softmax(-pk, axis=-1)], axis=-1)
        kv = torch.einsum('bhsf,bhsd->bhfd', phi_k, v)
        z = torch.einsum('bhsf->bhf', phi_k)
        num = torch.einsum('bhqf,bhfd->bhqd', phi_q, kv)
        den = torch.einsum('bhqf,bhf->bhq', phi_q, z)[..., None] + 1e-06
        o = num / den
        return (lambda x, *d: x.permute(*d))(o, 0, 2, 1, 3).reshape(B, S, D) @ wo

    def _B_ref(x, w_in, w_sp, b_sp, w_out):
        B, S, D = x.shape
        F = w_in.shape[-1]
        Fh = F // 2
        z = _gelu(torch.einsum('bsd,df->bsf', x, w_in))
        z1 = z[..., :Fh].clone()
        z2 = _layernorm(z[..., Fh:], axis=-1)
        g = torch.einsum('ts,bsf->btf', w_sp, z2) + b_sp[None, :, None]
        return torch.einsum('bsf,fd->bsd', z1 * g, w_out)
    x = A_x
    g = _sigmoid((x * gate_w).sum(-1, keepdims=True))
    a = _A_ref(x, A_wqkv, A_w_phi, A_wo)
    b = _B_ref(x, B_w_in, B_w_sp, B_b_sp, B_w_out)
    return g * a + (1 - g) * b
```

```cpp
#include <cuda_runtime.h>
#include <cuda_bf16.h>
#include <cuda.h>
#include <stdint.h>

namespace {

constexpr int SEQ = 2048, DM = 448, FH = 896, KALL = 1344;
constexpr int NP2 = 176;
constexpr int SLOT_BYTES = 49152;
constexpr int SPARE_OFF = 45056;
constexpr int X_OFF = 4 * SLOT_BYTES;
constexpr int BAR_OFF = X_OFF + 32768;
constexpr int SMEM_BYTES = BAR_OFF + 384 + 1024;
constexpr int NTHREADS = 384;
constexpr int OSTEP = 11;

__device__ __forceinline__ uint32_t g3off(int t) { return ((t + 6) % 12) * 16384; }
constexpr int POS_P1 = 0, POS_P2 = 7, POS_G2 = 14;

constexpr int FL_PREP = 0, FL_Z2N = 1, FL_KV = FL_Z2N + 64, FL_O = FL_KV + 8, FL_U = FL_O + 32, FL_COUNT = FL_U + 128;

constexpr int B_FULL = 0, B_EMPTY = 32, B_RDY1 = 64, B_RDY2 = 80, B_SIG = 96, B_FREE = 112, B_KVRDY = 128,
              B_PREP = 136, B_EP = 144, B_PIN = 152, B_KVIN = 160, B_XF1 = 168, B_XF2 = 184, B_ODONE = 200, B_EPVAL = 208,
              B_F3 = 216, B_OKO = 312, B_OKU = 320;

__device__ __align__(1024) __nv_bfloat16 g_Wp[8 * NP2 * DM];
__device__ __align__(1024) __nv_bfloat16 g_z2nT[FH * SEQ];
__device__ __align__(1024) uint4 g_U[16 * 8 * 2 * 7 * 128];
__device__ __align__(1024) uint2 g_O[16 * 8 * 2 * 7 * 128];
__device__ __align__(1024) float g_kv[16 * 64 * 32];
__device__ __align__(1024) unsigned long long g_stats[16 * 8 * 128];
__device__ __align__(1024) unsigned g_flags[FL_COUNT * 8];
__device__ unsigned g_epoch;

struct Params {
  const __nv_bfloat16* wphi;
  const __nv_bfloat16* bsp;
  const __nv_bfloat16* gatew;
};

__device__ __forceinline__ bool elect_one() {
  uint32_t p;
  asm volatile("{\n.reg .pred P;\nelect.sync _|P, 0xffffffff;\nselp.b32 %0, 1, 0, P;\n}" : "=r"(p));
  return p != 0;
}
__device__ __forceinline__ uint32_t smem_u32(const void* p) { return (uint32_t)__cvta_generic_to_shared(p); }
__device__ __forceinline__ void mbar_init(uint32_t bar, uint32_t cnt) {
  asm volatile("mbarrier.init.shared::cta.b64 [%0], %1;" ::"r"(bar), "r"(cnt) : "memory");
}
__device__ __forceinline__ void mbar_expect_tx(uint32_t bar, uint32_t bytes) {
  asm volatile("mbarrier.arrive.expect_tx.shared::cta.b64 _, [%0], %1;" ::"r"(bar), "r"(bytes) : "memory");
}
__device__ __forceinline__ void mbar_arrive(uint32_t bar) {
  asm volatile("mbarrier.arrive.shared::cta.b64 _, [%0];" ::"r"(bar) : "memory");
}
__device__ __forceinline__ uint32_t mapa(uint32_t addr, uint32_t cta) {
  uint32_t r;
  asm("mapa.shared::cluster.u32 %0, %1, %2;" : "=r"(r) : "r"(addr), "r"(cta));
  return r;
}
__device__ __forceinline__ void mbar_arrive_cluster(uint32_t remote_bar) {
  asm volatile("mbarrier.arrive.relaxed.cluster.shared::cluster.b64 _, [%0];" ::"r"(remote_bar) : "memory");
}
__device__ __forceinline__ void mbar_wait(uint32_t bar, uint32_t parity) {
  asm volatile("{\n.reg .pred p;\n.reg .u64 t0, t1;\n"
               "mbarrier.try_wait.parity.shared::cta.b64 p, [%0], %1;\n@p bra LAB_DONE;\nmov.u64 t0, %%clock64;\n"
               "LAB_WAIT:\nmbarrier.try_wait.parity.shared::cta.b64 p, [%0], %1;\n@p bra LAB_DONE;\n"
               "mov.u64 t1, %%clock64;\nsub.u64 t1, t1, t0;\nsetp.lt.u64 p, t1, 2000000000;\n@p bra LAB_WAIT;\ntrap;\nLAB_DONE:\n}"
               ::"r"(bar), "r"(parity) : "memory");
}
__device__ __forceinline__ void flag_wait(int idx, unsigned target) {
  asm volatile("{\n.reg .pred p;\n.reg .u32 n, v;\nmov.u32 n, 0;\n"
               "LAB_WAIT:\nld.acquire.gpu.global.u32 v, [%0];\nsub.u32 v, v, %1;\nsetp.ge.s32 p, v, 0;\n@p bra LAB_DONE;\n"
               "nanosleep.u32 20;\nadd.u32 n, n, 1;\nsetp.lt.u32 p, n, 262144;\n@p bra LAB_WAIT;\ntrap;\nLAB_DONE:\n}"
               ::"l"(g_flags + idx * 8), "r"(target) : "memory");
}
__device__ __forceinline__ void fence_async_global() { asm volatile("fence.proxy.async.global;" ::: "memory"); }
__device__ __forceinline__ void fence_async_smem() { asm volatile("fence.proxy.async.shared::cta;" ::: "memory"); }
__device__ __forceinline__ void bar_sync(int id, int n) { asm volatile("bar.sync %0, %1;" ::"r"(id), "r"(n) : "memory"); }
__device__ __forceinline__ void tma2d(uint32_t dst, const CUtensorMap* m, uint32_t bar, int c0, int c1) {
  asm volatile("cp.async.bulk.tensor.2d.shared::cluster.global.mbarrier::complete_tx::bytes [%0], [%1, {%3, %4}], [%2];"
               ::"r"(dst), "l"(m), "r"(bar), "r"(c0), "r"(c1) : "memory");
}
__device__ __forceinline__ void tma_store2d(const CUtensorMap* m, uint32_t src, int c0, int c1) {
  asm volatile("cp.async.bulk.tensor.2d.global.shared::cta.bulk_group [%0, {%2, %3}], [%1];" ::"l"(m), "r"(src), "r"(c0), "r"(c1) : "memory");
}
__device__ __forceinline__ void bulk_reduce_add_f32(float* dst, uint32_t src, uint32_t bytes) {
  asm volatile("cp.reduce.async.bulk.global.shared::cta.bulk_group.add.f32 [%0], [%1], %2;" ::"l"(dst), "r"(src), "r"(bytes) : "memory");
}
__device__ __forceinline__ void bulk_load(uint32_t dst, const void* src, uint32_t bytes, uint32_t bar) {
  asm volatile("cp.async.bulk.shared::cluster.global.mbarrier::complete_tx::bytes [%0], [%1], %2, [%3];" ::"r"(dst), "l"(src), "r"(bytes), "r"(bar) : "memory");
}
__device__ __forceinline__ void st_async4u(uint32_t raddr, uint32_t a, uint32_t b, uint32_t c, uint32_t d, uint32_t rbar) {
  asm volatile("st.async.weak.shared::cluster.mbarrier::complete_tx::bytes.v4.b32 [%0], {%1, %2, %3, %4}, [%5];"
               ::"r"(raddr), "r"(a), "r"(b), "r"(c), "r"(d), "r"(rbar) : "memory");
}
__device__ __forceinline__ void bulk_commit() { asm volatile("cp.async.bulk.commit_group;" ::: "memory"); }
__device__ __forceinline__ void bulk_wait_read() { asm volatile("cp.async.bulk.wait_group.read 0;" ::: "memory"); }
__device__ __forceinline__ void bulk_wait() { asm volatile("cp.async.bulk.wait_group 0;" ::: "memory"); }
__device__ __forceinline__ void sts32(uint32_t addr, uint32_t v) { asm volatile("st.shared.u32 [%0], %1;" ::"r"(addr), "r"(v) : "memory"); }
__device__ __forceinline__ uint32_t lds32(uint32_t addr) { uint32_t v; asm volatile("ld.shared.u32 %0, [%1];" : "=r"(v) : "r"(addr) : "memory"); return v; }
template <int N> __device__ __forceinline__ void pin_regs(uint32_t (&d)[N]) {
#pragma unroll
  for (int i = 0; i < N; i++) asm volatile("" : "+r"(d[i]));
}
__device__ __forceinline__ void poll_stats(const unsigned long long* p, uint32_t tag, unsigned long long (&v)[4]) {
  asm volatile("{\n.reg .pred p;\n.reg .u32 n, t, x;\n.reg .b32 lo, hi;\nmov.u32 n, 0;\n"
               "LAB_WAIT:\n"
               "ld.relaxed.gpu.global.b64 %0, [%4];\nld.relaxed.gpu.global.b64 %1, [%4 + 1024];\n"
               "ld.relaxed.gpu.global.b64 %2, [%4 + 64];\nld.relaxed.gpu.global.b64 %3, [%4 + 1088];\n"
               "mov.b64 {lo, hi}, %0;\nxor.b32 t, lo, %5;\n"
               "mov.b64 {lo, hi}, %1;\nxor.b32 x, lo, %5;\nor.b32 t, t, x;\n"
               "mov.b64 {lo, hi}, %2;\nxor.b32 x, lo, %5;\nor.b32 t, t, x;\n"
               "mov.b64 {lo, hi}, %3;\nxor.b32 x, lo, %5;\nor.b32 t, t, x;\n"
               "and.b32 t, t, 3;\nsetp.eq.u32 p, t, 0;\n@p bra LAB_DONE;\n"
               "add.u32 n, n, 1;\nsetp.lt.u32 p, n, 262144;\n@p bra LAB_WAIT;\ntrap;\nLAB_DONE:\n}"
               : "=&l"(v[0]), "=&l"(v[1]), "=&l"(v[2]), "=&l"(v[3]) : "l"(p), "r"(tag) : "memory");
}
__device__ __forceinline__ uint32_t tag_lo(uint32_t w, uint32_t tag) { return (w & ~1u) | (tag & 1u); }
__device__ __forceinline__ void st_unit16(uint4* p, uint32_t a, uint32_t b, uint32_t c, uint32_t d) {
  asm volatile("{\n.reg .b64 lo, hi;\n.reg .b128 t;\nmov.b64 lo, {%1, %2};\nmov.b64 hi, {%3, %4};\nmov.b128 t, {lo, hi};\n"
               "st.relaxed.gpu.global.b128 [%0], t;\n}" ::"l"(p), "r"(a), "r"(b), "r"(c), "r"(d) : "memory");
}
__device__ __forceinline__ void st_unit8(uint2* p, uint32_t a, uint32_t b) {
  asm volatile("{\n.reg .b64 lo;\nmov.b64 lo, {%1, %2};\nst.relaxed.gpu.global.b64 [%0], lo;\n}" ::"l"(p), "r"(a), "r"(b) : "memory");
}
__device__ __forceinline__ void u_load(const uint4* p, uint32_t (&v)[28]) {
  asm volatile("{\n.reg .b64 lo, hi;\n.reg .b128 t;\n"
               "ld.relaxed.gpu.global.b128 t, [%28 + 0];\nmov.b128 {lo, hi}, t;\nmov.b64 {%0, %1}, lo;\nmov.b64 {%2, %3}, hi;\n"
               "ld.relaxed.gpu.global.b128 t, [%28 + 2048];\nmov.b128 {lo, hi}, t;\nmov.b64 {%4, %5}, lo;\nmov.b64 {%6, %7}, hi;\n"
               "ld.relaxed.gpu.global.b128 t, [%28 + 4096];\nmov.b128 {lo, hi}, t;\nmov.b64 {%8, %9}, lo;\nmov.b64 {%10, %11}, hi;\n"
               "ld.relaxed.gpu.global.b128 t, [%28 + 6144];\nmov.b128 {lo, hi}, t;\nmov.b64 {%12, %13}, lo;\nmov.b64 {%14, %15}, hi;\n"
               "ld.relaxed.gpu.global.b128 t, [%28 + 8192];\nmov.b128 {lo, hi}, t;\nmov.b64 {%16, %17}, lo;\nmov.b64 {%18, %19}, hi;\n"
               "ld.relaxed.gpu.global.b128 t, [%28 + 10240];\nmov.b128 {lo, hi}, t;\nmov.b64 {%20, %21}, lo;\nmov.b64 {%22, %23}, hi;\n"
               "ld.relaxed.gpu.global.b128 t, [%28 + 12288];\nmov.b128 {lo, hi}, t;\nmov.b64 {%24, %25}, lo;\nmov.b64 {%26, %27}, hi;\n"
               "}" : "=r"(v[0]), "=r"(v[1]), "=r"(v[2]), "=r"(v[3]), "=r"(v[4]), "=r"(v[5]), "=r"(v[6]), "=r"(v[7]), "=r"(v[8]), "=r"(v[9]), "=r"(v[10]), "=r"(v[11]), "=r"(v[12]), "=r"(v[13]), "=r"(v[14]), "=r"(v[15]), "=r"(v[16]), "=r"(v[17]), "=r"(v[18]), "=r"(v[19]), "=r"(v[20]), "=r"(v[21]), "=r"(v[22]), "=r"(v[23]), "=r"(v[24]), "=r"(v[25]), "=r"(v[26]), "=r"(v[27]) : "l"(p) : "memory");
}
__device__ __forceinline__ void u_poll(const uint4* p, uint32_t tag) {
  asm volatile("{\n.reg .pred p;\n.reg .u32 bad, x, t0;\n.reg .u32 v<7>;\nmov.u32 t0, %%clock;\nLAB_WAIT:\n"
               "ld.relaxed.gpu.global.b32 v0, [%0 + 0];\n"
               "ld.relaxed.gpu.global.b32 v1, [%0 + 2048];\n"
               "ld.relaxed.gpu.global.b32 v2, [%0 + 4096];\n"
               "ld.relaxed.gpu.global.b32 v3, [%0 + 6144];\n"
               "ld.relaxed.gpu.global.b32 v4, [%0 + 8192];\n"
               "ld.relaxed.gpu.global.b32 v5, [%0 + 10240];\n"
               "ld.relaxed.gpu.global.b32 v6, [%0 + 12288];\n"
               "xor.b32 bad, v0, %1;\n"
               "xor.b32 v1, v1, %1;\nor.b32 bad, bad, v1;\n"
               "xor.b32 v2, v2, %1;\nor.b32 bad, bad, v2;\n"
               "xor.b32 v3, v3, %1;\nor.b32 bad, bad, v3;\n"
               "xor.b32 v4, v4, %1;\nor.b32 bad, bad, v4;\n"
               "xor.b32 v5, v5, %1;\nor.b32 bad, bad, v5;\n"
               "xor.b32 v6, v6, %1;\nor.b32 bad, bad, v6;\n"
               "and.b32 bad, bad, 1;\nsetp.eq.u32 p, bad, 0;\nvote.sync.all.pred p, p, 0xffffffff;\n@p bra LAB_DONE;\n"
               "mov.u32 x, %%clock;\nsub.u32 x, x, t0;\nsetp.lt.u32 p, x, 2000000000;\n@p bra LAB_WAIT;\ntrap;\nLAB_DONE:\n}"
               :: "l"(p), "r"(tag) : "memory");
}
__device__ __forceinline__ void o_poll(const uint2* p0, const uint2* p1, uint32_t tag) {
  asm volatile("{\n.reg .pred p;\n.reg .u32 bad, x, t0;\n.reg .u32 v<14>;\nmov.u32 t0, %%clock;\nLAB_WAIT:\n"
               "ld.relaxed.gpu.global.b32 v0, [%0 + 0];\n"
               "ld.relaxed.gpu.global.b32 v1, [%0 + 1024];\n"
               "ld.relaxed.gpu.global.b32 v2, [%0 + 2048];\n"
               "ld.relaxed.gpu.global.b32 v3, [%0 + 3072];\n"
               "ld.relaxed.gpu.global.b32 v4, [%0 + 4096];\n"
               "ld.relaxed.gpu.global.b32 v5, [%0 + 5120];\n"
               "ld.relaxed.gpu.global.b32 v6, [%0 + 6144];\n"
               "ld.relaxed.gpu.global.b32 v7, [%1 + 0];\n"
               "ld.relaxed.gpu.global.b32 v8, [%1 + 1024];\n"
               "ld.relaxed.gpu.global.b32 v9, [%1 + 2048];\n"
               "ld.relaxed.gpu.global.b32 v10, [%1 + 3072];\n"
               "ld.relaxed.gpu.global.b32 v11, [%1 + 4096];\n"
               "ld.relaxed.gpu.global.b32 v12, [%1 + 5120];\n"
               "ld.relaxed.gpu.global.b32 v13, [%1 + 6144];\n"
               "xor.b32 bad, v0, %2;\n"
               "xor.b32 v1, v1, %2;\nor.b32 bad, bad, v1;\n"
               "xor.b32 v2, v2, %2;\nor.b32 bad, bad, v2;\n"
               "xor.b32 v3, v3, %2;\nor.b32 bad, bad, v3;\n"
               "xor.b32 v4, v4, %2;\nor.b32 bad, bad, v4;\n"
               "xor.b32 v5, v5, %2;\nor.b32 bad, bad, v5;\n"
               "xor.b32 v6, v6, %2;\nor.b32 bad, bad, v6;\n"
               "xor.b32 v7, v7, %2;\nor.b32 bad, bad, v7;\n"
               "xor.b32 v8, v8, %2;\nor.b32 bad, bad, v8;\n"
               "xor.b32 v9, v9, %2;\nor.b32 bad, bad, v9;\n"
               "xor.b32 v10, v10, %2;\nor.b32 bad, bad, v10;\n"
               "xor.b32 v11, v11, %2;\nor.b32 bad, bad, v11;\n"
               "xor.b32 v12, v12, %2;\nor.b32 bad, bad, v12;\n"
               "xor.b32 v13, v13, %2;\nor.b32 bad, bad, v13;\n"
               "and.b32 bad, bad, 1;\nsetp.eq.u32 p, bad, 0;\nvote.sync.all.pred p, p, 0xffffffff;\n@p bra LAB_DONE;\n"
               "mov.u32 x, %%clock;\nsub.u32 x, x, t0;\nsetp.lt.u32 p, x, 2000000000;\n@p bra LAB_WAIT;\ntrap;\nLAB_DONE:\n}"
               :: "l"(p0), "l"(p1), "r"(tag) : "memory");
}
__device__ __forceinline__ void o_load(const uint2* p0, const uint2* p1, uint32_t (&v)[28]) {
  asm volatile("{\n.reg .b64 lo;\n"
               "ld.relaxed.gpu.global.b64 lo, [%28 + 0];\nmov.b64 {%0, %1}, lo;\n"
               "ld.relaxed.gpu.global.b64 lo, [%28 + 1024];\nmov.b64 {%2, %3}, lo;\n"
               "ld.relaxed.gpu.global.b64 lo, [%28 + 2048];\nmov.b64 {%4, %5}, lo;\n"
               "ld.relaxed.gpu.global.b64 lo, [%28 + 3072];\nmov.b64 {%6, %7}, lo;\n"
               "ld.relaxed.gpu.global.b64 lo, [%28 + 4096];\nmov.b64 {%8, %9}, lo;\n"
               "ld.relaxed.gpu.global.b64 lo, [%28 + 5120];\nmov.b64 {%10, %11}, lo;\n"
               "ld.relaxed.gpu.global.b64 lo, [%28 + 6144];\nmov.b64 {%12, %13}, lo;\n"
               "ld.relaxed.gpu.global.b64 lo, [%29 + 0];\nmov.b64 {%14, %15}, lo;\n"
               "ld.relaxed.gpu.global.b64 lo, [%29 + 1024];\nmov.b64 {%16, %17}, lo;\n"
               "ld.relaxed.gpu.global.b64 lo, [%29 + 2048];\nmov.b64 {%18, %19}, lo;\n"
               "ld.relaxed.gpu.global.b64 lo, [%29 + 3072];\nmov.b64 {%20, %21}, lo;\n"
               "ld.relaxed.gpu.global.b64 lo, [%29 + 4096];\nmov.b64 {%22, %23}, lo;\n"
               "ld.relaxed.gpu.global.b64 lo, [%29 + 5120];\nmov.b64 {%24, %25}, lo;\n"
               "ld.relaxed.gpu.global.b64 lo, [%29 + 6144];\nmov.b64 {%26, %27}, lo;\n"
               "}" : "=r"(v[0]), "=r"(v[1]), "=r"(v[2]), "=r"(v[3]), "=r"(v[4]), "=r"(v[5]), "=r"(v[6]), "=r"(v[7]), "=r"(v[8]), "=r"(v[9]), "=r"(v[10]), "=r"(v[11]), "=r"(v[12]), "=r"(v[13]), "=r"(v[14]), "=r"(v[15]), "=r"(v[16]), "=r"(v[17]), "=r"(v[18]), "=r"(v[19]), "=r"(v[20]), "=r"(v[21]), "=r"(v[22]), "=r"(v[23]), "=r"(v[24]), "=r"(v[25]), "=r"(v[26]), "=r"(v[27]) : "l"(p0), "l"(p1) : "memory");
}
__device__ __forceinline__ void prefetch_map(const CUtensorMap* m) {
  asm volatile("prefetch.tensormap [%0];" ::"l"(m) : "memory");
}
__device__ __forceinline__ void wg_fence() { asm volatile("wgmma.fence.sync.aligned;" ::: "memory"); }
__device__ __forceinline__ void wg_commit() { asm volatile("wgmma.commit_group.sync.aligned;" ::: "memory"); }
template <int N> __device__ __forceinline__ void wg_wait() { asm volatile("wgmma.wait_group.sync.aligned %0;" ::"n"(N) : "memory"); }
template <int N> __device__ __forceinline__ void fence_acc(float (&d)[N]) {
#pragma unroll
  for (int i = 0; i < N; i++) asm volatile("" : "+f"(d[i])::"memory");
}
__device__ __forceinline__ uint64_t desc128(uint32_t addr, uint32_t lbo_bytes) {
  return (uint64_t)((addr & 0x3FFFF) >> 4) | ((uint64_t)(lbo_bytes >> 4) << 16) | ((uint64_t)(1024 >> 4) << 32) | (1ull << 62);
}
__device__ __forceinline__ uint32_t pack_bf16(float lo, float hi) {
  uint32_t r;
  asm("cvt.rn.bf16x2.f32 %0, %1, %2;" : "=r"(r) : "f"(hi), "f"(lo));
  return r;
}
__device__ __forceinline__ float bf_lo(uint32_t v) { return __uint_as_float(v << 16); }
__device__ __forceinline__ float bf_hi(uint32_t v) { return __uint_as_float(v & 0xffff0000u); }
__device__ __forceinline__ void stsm4(uint32_t addr, uint32_t a, uint32_t b, uint32_t c, uint32_t d) {
  asm volatile("stmatrix.sync.aligned.m8n8.x4.shared.b16 [%0], {%1, %2, %3, %4};" ::"r"(addr), "r"(a), "r"(b), "r"(c), "r"(d) : "memory");
}
__device__ __forceinline__ void stsm4t(uint32_t addr, uint32_t a, uint32_t b, uint32_t c, uint32_t d) {
  asm volatile("stmatrix.sync.aligned.m8n8.x4.trans.shared.b16 [%0], {%1, %2, %3, %4};" ::"r"(addr), "r"(a), "r"(b), "r"(c), "r"(d) : "memory");
}
__device__ __forceinline__ void stsm2(uint32_t addr, uint32_t a, uint32_t b) {
  asm volatile("stmatrix.sync.aligned.m8n8.x2.shared.b16 [%0], {%1, %2};" ::"r"(addr), "r"(a), "r"(b) : "memory");
}
__device__ __forceinline__ uint4 lds128(uint32_t addr) {
  uint4 v;
  asm volatile("ld.shared.v4.u32 {%0, %1, %2, %3}, [%4];" : "=r"(v.x), "=r"(v.y), "=r"(v.z), "=r"(v.w) : "r"(addr) : "memory");
  return v;
}
__device__ __forceinline__ void sts128(uint32_t addr, uint32_t a, uint32_t b, uint32_t c, uint32_t d) {
  asm volatile("st.shared.v4.u32 [%0], {%1, %2, %3, %4};" ::"r"(addr), "r"(a), "r"(b), "r"(c), "r"(d) : "memory");
}
__device__ __forceinline__ float ex2(float x) { float y; asm("ex2.approx.ftz.f32 %0, %1;" : "=f"(y) : "f"(x)); return y; }
__device__ __forceinline__ float rcp(float x) { float y; asm("rcp.approx.ftz.f32 %0, %1;" : "=f"(y) : "f"(x)); return y; }
__device__ __forceinline__ float gelu_tanh(float x) {
  const float k0 = 0.7978845608028654f, k1 = 0.7978845608028654f * 0.044715f;
  float u = x * fmaf(x * x, k1, k0), t;
  asm("tanh.approx.f32 %0, %1;" : "=f"(t) : "f"(u));
  return x * fmaf(t, 0.5f, 0.5f);
}
__device__ __forceinline__ void mma16816(float (&d)[4], const uint32_t (&a)[4], uint32_t b0, uint32_t b1) {
  asm volatile("mma.sync.aligned.m16n8k16.row.col.f32.bf16.bf16.f32 {%0, %1, %2, %3}, {%4, %5, %6, %7}, {%8, %9}, {%0, %1, %2, %3};"
               : "+f"(d[0]), "+f"(d[1]), "+f"(d[2]), "+f"(d[3])
               : "r"(a[0]), "r"(a[1]), "r"(a[2]), "r"(a[3]), "r"(b0), "r"(b1));
}

template <int TA, int TB>
__device__ __forceinline__ void wgmma_ss_n32(float (&d)[16], uint64_t da, uint64_t db, int scale_d) {
  asm volatile("{\n.reg .pred p;\nsetp.ne.b32 p, %18, 0;\n"
    "wgmma.mma_async.sync.aligned.m64n32k16.f32.bf16.bf16 "
    "{%0, %1, %2, %3, %4, %5, %6, %7, %8, %9, %10, %11, %12, %13, %14, %15}, %16, %17, p, 1, 1, %19, %20;\n}\n"
    : "+f"(d[0]), "+f"(d[1]), "+f"(d[2]), "+f"(d[3]), "+f"(d[4]), "+f"(d[5]), "+f"(d[6]), "+f"(d[7]), "+f"(d[8]), "+f"(d[9]), "+f"(d[10]), "+f"(d[11]), "+f"(d[12]), "+f"(d[13]), "+f"(d[14]), "+f"(d[15])
    : "l"(da), "l"(db), "r"(scale_d), "n"(TA), "n"(TB));
}

template <int TA, int TB>
__device__ __forceinline__ void wgmma_ss_n176(float (&d)[88], uint64_t da, uint64_t db, int scale_d) {
  asm volatile("{\n.reg .pred p;\nsetp.ne.b32 p, %90, 0;\n"
    "wgmma.mma_async.sync.aligned.m64n176k16.f32.bf16.bf16 "
    "{%0, %1, %2, %3, %4, %5, %6, %7, %8, %9, %10, %11, %12, %13, %14, %15, %16, %17, %18, %19, %20, %21, %22, %23, %24, %25, %26, %27, %28, %29, %30, %31, %32, %33, %34, %35, %36, %37, %38, %39, %40, %41, %42, %43, %44, %45, %46, %47, %48, %49, %50, %51, %52, %53, %54, %55, %56, %57, %58, %59, %60, %61, %62, %63, %64, %65, %66, %67, %68, %69, %70, %71, %72, %73, %74, %75, %76, %77, %78, %79, %80, %81, %82, %83, %84, %85, %86, %87}, %88, %89, p, 1, 1, %91, %92;\n}\n"
    : "+f"(d[0]), "+f"(d[1]), "+f"(d[2]), "+f"(d[3]), "+f"(d[4]), "+f"(d[5]), "+f"(d[6]), "+f"(d[7]), "+f"(d[8]), "+f"(d[9]), "+f"(d[10]), "+f"(d[11]), "+f"(d[12]), "+f"(d[13]), "+f"(d[14]), "+f"(d[15]), "+f"(d[16]), "+f"(d[17]), "+f"(d[18]), "+f"(d[19]), "+f"(d[20]), "+f"(d[21]), "+f"(d[22]), "+f"(d[23]), "+f"(d[24]), "+f"(d[25]), "+f"(d[26]), "+f"(d[27]), "+f"(d[28]), "+f"(d[29]), "+f"(d[30]), "+f"(d[31]), "+f"(d[32]), "+f"(d[33]), "+f"(d[34]), "+f"(d[35]), "+f"(d[36]), "+f"(d[37]), "+f"(d[38]), "+f"(d[39]), "+f"(d[40]), "+f"(d[41]), "+f"(d[42]), "+f"(d[43]), "+f"(d[44]), "+f"(d[45]), "+f"(d[46]), "+f"(d[47]), "+f"(d[48]), "+f"(d[49]), "+f"(d[50]), "+f"(d[51]), "+f"(d[52]), "+f"(d[53]), "+f"(d[54]), "+f"(d[55]), "+f"(d[56]), "+f"(d[57]), "+f"(d[58]), "+f"(d[59]), "+f"(d[60]), "+f"(d[61]), "+f"(d[62]), "+f"(d[63]), "+f"(d[64]), "+f"(d[65]), "+f"(d[66]), "+f"(d[67]), "+f"(d[68]), "+f"(d[69]), "+f"(d[70]), "+f"(d[71]), "+f"(d[72]), "+f"(d[73]), "+f"(d[74]), "+f"(d[75]), "+f"(d[76]), "+f"(d[77]), "+f"(d[78]), "+f"(d[79]), "+f"(d[80]), "+f"(d[81]), "+f"(d[82]), "+f"(d[83]), "+f"(d[84]), "+f"(d[85]), "+f"(d[86]), "+f"(d[87])
    : "l"(da), "l"(db), "r"(scale_d), "n"(TA), "n"(TB));
}

template <int TA, int TB>
__device__ __forceinline__ void wgmma_ss_n224(float (&d)[112], uint64_t da, uint64_t db, int scale_d) {
  asm volatile("{\n.reg .pred p;\nsetp.ne.b32 p, %114, 0;\n"
    "wgmma.mma_async.sync.aligned.m64n224k16.f32.bf16.bf16 "
    "{%0, %1, %2, %3, %4, %5, %6, %7, %8, %9, %10, %11, %12, %13, %14, %15, %16, %17, %18, %19, %20, %21, %22, %23, %24, %25, %26, %27, %28, %29, %30, %31, %32, %33, %34, %35, %36, %37, %38, %39, %40, %41, %42, %43, %44, %45, %46, %47, %48, %49, %50, %51, %52, %53, %54, %55, %56, %57, %58, %59, %60, %61, %62, %63, %64, %65, %66, %67, %68, %69, %70, %71, %72, %73, %74, %75, %76, %77, %78, %79, %80, %81, %82, %83, %84, %85, %86, %87, %88, %89, %90, %91, %92, %93, %94, %95, %96, %97, %98, %99, %100, %101, %102, %103, %104, %105, %106, %107, %108, %109, %110, %111}, %112, %113, p, 1, 1, %115, %116;\n}\n"
    : "+f"(d[0]), "+f"(d[1]), "+f"(d[2]), "+f"(d[3]), "+f"(d[4]), "+f"(d[5]), "+f"(d[6]), "+f"(d[7]), "+f"(d[8]), "+f"(d[9]), "+f"(d[10]), "+f"(d[11]), "+f"(d[12]), "+f"(d[13]), "+f"(d[14]), "+f"(d[15]), "+f"(d[16]), "+f"(d[17]), "+f"(d[18]), "+f"(d[19]), "+f"(d[20]), "+f"(d[21]), "+f"(d[22]), "+f"(d[23]), "+f"(d[24]), "+f"(d[25]), "+f"(d[26]), "+f"(d[27]), "+f"(d[28]), "+f"(d[29]), "+f"(d[30]), "+f"(d[31]), "+f"(d[32]), "+f"(d[33]), "+f"(d[34]), "+f"(d[35]), "+f"(d[36]), "+f"(d[37]), "+f"(d[38]), "+f"(d[39]), "+f"(d[40]), "+f"(d[41]), "+f"(d[42]), "+f"(d[43]), "+f"(d[44]), "+f"(d[45]), "+f"(d[46]), "+f"(d[47]), "+f"(d[48]), "+f"(d[49]), "+f"(d[50]), "+f"(d[51]), "+f"(d[52]), "+f"(d[53]), "+f"(d[54]), "+f"(d[55]), "+f"(d[56]), "+f"(d[57]), "+f"(d[58]), "+f"(d[59]), "+f"(d[60]), "+f"(d[61]), "+f"(d[62]), "+f"(d[63]), "+f"(d[64]), "+f"(d[65]), "+f"(d[66]), "+f"(d[67]), "+f"(d[68]), "+f"(d[69]), "+f"(d[70]), "+f"(d[71]), "+f"(d[72]), "+f"(d[73]), "+f"(d[74]), "+f"(d[75]), "+f"(d[76]), "+f"(d[77]), "+f"(d[78]), "+f"(d[79]), "+f"(d[80]), "+f"(d[81]), "+f"(d[82]), "+f"(d[83]), "+f"(d[84]), "+f"(d[85]), "+f"(d[86]), "+f"(d[87]), "+f"(d[88]), "+f"(d[89]), "+f"(d[90]), "+f"(d[91]), "+f"(d[92]), "+f"(d[93]), "+f"(d[94]), "+f"(d[95]), "+f"(d[96]), "+f"(d[97]), "+f"(d[98]), "+f"(d[99]), "+f"(d[100]), "+f"(d[101]), "+f"(d[102]), "+f"(d[103]), "+f"(d[104]), "+f"(d[105]), "+f"(d[106]), "+f"(d[107]), "+f"(d[108]), "+f"(d[109]), "+f"(d[110]), "+f"(d[111])
    : "l"(da), "l"(db), "r"(scale_d), "n"(TA), "n"(TB));
}

template <int TA, int TB>
__device__ __forceinline__ void wgmma_ss_n240(float (&d)[120], uint64_t da, uint64_t db, int scale_d) {
  asm volatile("{\n.reg .pred p;\nsetp.ne.b32 p, %122, 0;\n"
    "wgmma.mma_async.sync.aligned.m64n240k16.f32.bf16.bf16 "
    "{%0, %1, %2, %3, %4, %5, %6, %7, %8, %9, %10, %11, %12, %13, %14, %15, %16, %17, %18, %19, %20, %21, %22, %23, %24, %25, %26, %27, %28, %29, %30, %31, %32, %33, %34, %35, %36, %37, %38, %39, %40, %41, %42, %43, %44, %45, %46, %47, %48, %49, %50, %51, %52, %53, %54, %55, %56, %57, %58, %59, %60, %61, %62, %63, %64, %65, %66, %67, %68, %69, %70, %71, %72, %73, %74, %75, %76, %77, %78, %79, %80, %81, %82, %83, %84, %85, %86, %87, %88, %89, %90, %91, %92, %93, %94, %95, %96, %97, %98, %99, %100, %101, %102, %103, %104, %105, %106, %107, %108, %109, %110, %111, %112, %113, %114, %115, %116, %117, %118, %119}, %120, %121, p, 1, 1, %123, %124;\n}\n"
    : "+f"(d[0]), "+f"(d[1]), "+f"(d[2]), "+f"(d[3]), "+f"(d[4]), "+f"(d[5]), "+f"(d[6]), "+f"(d[7]), "+f"(d[8]), "+f"(d[9]), "+f"(d[10]), "+f"(d[11]), "+f"(d[12]), "+f"(d[13]), "+f"(d[14]), "+f"(d[15]), "+f"(d[16]), "+f"(d[17]), "+f"(d[18]), "+f"(d[19]), "+f"(d[20]), "+f"(d[21]), "+f"(d[22]), "+f"(d[23]), "+f"(d[24]), "+f"(d[25]), "+f"(d[26]), "+f"(d[27]), "+f"(d[28]), "+f"(d[29]), "+f"(d[30]), "+f"(d[31]), "+f"(d[32]), "+f"(d[33]), "+f"(d[34]), "+f"(d[35]), "+f"(d[36]), "+f"(d[37]), "+f"(d[38]), "+f"(d[39]), "+f"(d[40]), "+f"(d[41]), "+f"(d[42]), "+f"(d[43]), "+f"(d[44]), "+f"(d[45]), "+f"(d[46]), "+f"(d[47]), "+f"(d[48]), "+f"(d[49]), "+f"(d[50]), "+f"(d[51]), "+f"(d[52]), "+f"(d[53]), "+f"(d[54]), "+f"(d[55]), "+f"(d[56]), "+f"(d[57]), "+f"(d[58]), "+f"(d[59]), "+f"(d[60]), "+f"(d[61]), "+f"(d[62]), "+f"(d[63]), "+f"(d[64]), "+f"(d[65]), "+f"(d[66]), "+f"(d[67]), "+f"(d[68]), "+f"(d[69]), "+f"(d[70]), "+f"(d[71]), "+f"(d[72]), "+f"(d[73]), "+f"(d[74]), "+f"(d[75]), "+f"(d[76]), "+f"(d[77]), "+f"(d[78]), "+f"(d[79]), "+f"(d[80]), "+f"(d[81]), "+f"(d[82]), "+f"(d[83]), "+f"(d[84]), "+f"(d[85]), "+f"(d[86]), "+f"(d[87]), "+f"(d[88]), "+f"(d[89]), "+f"(d[90]), "+f"(d[91]), "+f"(d[92]), "+f"(d[93]), "+f"(d[94]), "+f"(d[95]), "+f"(d[96]), "+f"(d[97]), "+f"(d[98]), "+f"(d[99]), "+f"(d[100]), "+f"(d[101]), "+f"(d[102]), "+f"(d[103]), "+f"(d[104]), "+f"(d[105]), "+f"(d[106]), "+f"(d[107]), "+f"(d[108]), "+f"(d[109]), "+f"(d[110]), "+f"(d[111]), "+f"(d[112]), "+f"(d[113]), "+f"(d[114]), "+f"(d[115]), "+f"(d[116]), "+f"(d[117]), "+f"(d[118]), "+f"(d[119])
    : "l"(da), "l"(db), "r"(scale_d), "n"(TA), "n"(TB));
}

template <int TB>
__device__ __forceinline__ void wgmma_rs_n32(float (&d)[16], uint32_t a0, uint32_t a1, uint32_t a2, uint32_t a3, uint64_t db, int scale_d) {
  asm volatile("{\n.reg .pred p;\nsetp.ne.b32 p, %21, 0;\n"
    "wgmma.mma_async.sync.aligned.m64n32k16.f32.bf16.bf16 "
    "{%0, %1, %2, %3, %4, %5, %6, %7, %8, %9, %10, %11, %12, %13, %14, %15}, {%16, %17, %18, %19}, %20, p, 1, 1, %22;\n}\n"
    : "+f"(d[0]), "+f"(d[1]), "+f"(d[2]), "+f"(d[3]), "+f"(d[4]), "+f"(d[5]), "+f"(d[6]), "+f"(d[7]), "+f"(d[8]), "+f"(d[9]), "+f"(d[10]), "+f"(d[11]), "+f"(d[12]), "+f"(d[13]), "+f"(d[14]), "+f"(d[15])
    : "r"(a0), "r"(a1), "r"(a2), "r"(a3), "l"(db), "r"(scale_d), "n"(TB));
}

template <int TB>
__device__ __forceinline__ void wgmma_rs_n112(float (&d)[56], uint32_t a0, uint32_t a1, uint32_t a2, uint32_t a3, uint64_t db, int scale_d) {
  asm volatile("{\n.reg .pred p;\nsetp.ne.b32 p, %61, 0;\n"
    "wgmma.mma_async.sync.aligned.m64n112k16.f32.bf16.bf16 "
    "{%0, %1, %2, %3, %4, %5, %6, %7, %8, %9, %10, %11, %12, %13, %14, %15, %16, %17, %18, %19, %20, %21, %22, %23, %24, %25, %26, %27, %28, %29, %30, %31, %32, %33, %34, %35, %36, %37, %38, %39, %40, %41, %42, %43, %44, %45, %46, %47, %48, %49, %50, %51, %52, %53, %54, %55}, {%56, %57, %58, %59}, %60, p, 1, 1, %62;\n}\n"
    : "+f"(d[0]), "+f"(d[1]), "+f"(d[2]), "+f"(d[3]), "+f"(d[4]), "+f"(d[5]), "+f"(d[6]), "+f"(d[7]), "+f"(d[8]), "+f"(d[9]), "+f"(d[10]), "+f"(d[11]), "+f"(d[12]), "+f"(d[13]), "+f"(d[14]), "+f"(d[15]), "+f"(d[16]), "+f"(d[17]), "+f"(d[18]), "+f"(d[19]), "+f"(d[20]), "+f"(d[21]), "+f"(d[22]), "+f"(d[23]), "+f"(d[24]), "+f"(d[25]), "+f"(d[26]), "+f"(d[27]), "+f"(d[28]), "+f"(d[29]), "+f"(d[30]), "+f"(d[31]), "+f"(d[32]), "+f"(d[33]), "+f"(d[34]), "+f"(d[35]), "+f"(d[36]), "+f"(d[37]), "+f"(d[38]), "+f"(d[39]), "+f"(d[40]), "+f"(d[41]), "+f"(d[42]), "+f"(d[43]), "+f"(d[44]), "+f"(d[45]), "+f"(d[46]), "+f"(d[47]), "+f"(d[48]), "+f"(d[49]), "+f"(d[50]), "+f"(d[51]), "+f"(d[52]), "+f"(d[53]), "+f"(d[54]), "+f"(d[55])
    : "r"(a0), "r"(a1), "r"(a2), "r"(a3), "l"(db), "r"(scale_d), "n"(TB));
}


__device__ __forceinline__ void feature_map(const float (&v)[7], uint32_t (&o)[8]) {
  const float L2E = 1.4426950408889634f;
  float mx = v[0], mn = v[0];
#pragma unroll
  for (int g = 1; g < 7; g++) { mx = fmaxf(mx, v[g]); mn = fminf(mn, v[g]); }
  mx = fmaxf(mx, __shfl_xor_sync(0xffffffffu, mx, 1));
  mn = fminf(mn, __shfl_xor_sync(0xffffffffu, mn, 1));
  mx = fmaxf(mx, __shfl_xor_sync(0xffffffffu, mx, 2));
  mn = fminf(mn, __shfl_xor_sync(0xffffffffu, mn, 2));
  const float a = -mx * L2E, b = mn * L2E;
  float p[7], n[7], sp = 0.f, sn = 0.f;
#pragma unroll
  for (int g = 0; g < 7; g++) {
    p[g] = ex2(fmaf(v[g], L2E, a));
    n[g] = ex2(fmaf(v[g], -L2E, b));
    sp += p[g];
    sn += n[g];
  }
  sp += __shfl_xor_sync(0xffffffffu, sp, 1);
  sn += __shfl_xor_sync(0xffffffffu, sn, 1);
  sp += __shfl_xor_sync(0xffffffffu, sp, 2);
  sn += __shfl_xor_sync(0xffffffffu, sn, 2);
  const float rp = rcp(sp), rn = rcp(sn);
  o[0] = pack_bf16(p[0] * rp, p[1] * rp);
  o[1] = pack_bf16(p[2] * rp, p[3] * rp);
  o[2] = pack_bf16(p[4] * rp, p[5] * rp);
  o[3] = pack_bf16(p[6] * rp, 0.f);
  o[4] = pack_bf16(n[0] * rn, n[1] * rn);
  o[5] = pack_bf16(n[2] * rn, n[3] * rn);
  o[6] = pack_bf16(n[4] * rn, n[5] * rn);
  o[7] = pack_bf16(n[6] * rn, 0.f);
}

struct Maps {
  CUtensorMap x, win, wp, wsp, z, wo, wout, ost, wq, wps;
  CUtensorMap win48, wo48, wo64h, wo48h, wout48, wout64h, wout48h;
};

__device__ __forceinline__ void issue_p1(const Maps& mp, uint32_t sb, int m, int i, int j) {
  const int c0 = FH + 112 * j, c1 = 112 * j;
  const uint32_t dst = sb + (m & 3) * SLOT_BYTES, full = sb + BAR_OFF + B_FULL + 8 * (m & 3);
  mbar_expect_tx(full, 16384 + 2 * (8192 + 6144));
  tma2d(dst, &mp.x, full, 64 * m, 128 * i);
  tma2d(dst + 16384, &mp.win, full, c0, 64 * m);
  tma2d(dst + 16384 + 8192, &mp.win48, full, c0 + 64, 64 * m);
  tma2d(dst + 16384 + 16384, &mp.win, full, c1, 64 * m);
  tma2d(dst + 16384 + 24576, &mp.win48, full, c1 + 64, 64 * m);
}

__device__ __forceinline__ void producer(const Maps& mp, uint32_t sb, int i, int j) {
  const int p = j >> 1, c = j & 1;
  const uint32_t bars = sb + BAR_OFF;
  auto full = [&](int pos) { return bars + B_FULL + 8 * (pos & 3); };
  auto acquire = [&](int pos) { mbar_wait(bars + B_EMPTY + 8 * (pos & 3), ((pos >> 2) - 1) & 1); };
#pragma unroll 1
  for (int m = 4; m < 7; m++) { acquire(m); issue_p1(mp, sb, m, i, j); }
  mbar_wait(bars + B_EP, 0);
  const unsigned e1 = lds32(bars + B_EPVAL) + 1;
#pragma unroll 1
  for (int m = 0; m < 7; m++) {
    const int pos = POS_P2 + m;
    acquire(pos);
    const uint32_t dst = sb + (pos & 3) * SLOT_BYTES;
    const int kb = m < 4 ? m + 3 : m - 4;
    mbar_expect_tx(full(pos), (m < 4 ? 0 : 16384) + 169 * 128);
    if (m >= 4) tma2d(dst, &mp.x, full(pos), 64 * kb, 128 * i);
    if (m == 0) { flag_wait(FL_PREP, 128 * e1); fence_async_global(); }
    tma2d(dst + 16384, &mp.wp, full(pos), 64 * kb, NP2 * j);
  }
#pragma unroll 1
  for (int m = 0; m < 16; m++) {
    const int pos = POS_G2 + m;
    acquire(pos);
    const uint32_t dst = sb + (pos & 3) * SLOT_BYTES;
    mbar_expect_tx(full(pos), 16384 + 224 * 128);
    tma2d(dst, &mp.wsp, full(pos), 1024 * c + 64 * m, 128 * i);
    if ((m & 1) == 0) { flag_wait(FL_Z2N + (8 * c + (m >> 1)) * 4 + p, 4 * e1); fence_async_global(); }
    tma2d(dst + 16384, &mp.z, full(pos), 1024 * c + 64 * m, 112 * j);
    tma2d(dst + 16384 + 14336, &mp.z, full(pos), 1024 * c + 64 * m, 112 * (j ^ 1));
  }
  auto g2_released = [&](int pos) { mbar_wait(bars + B_EMPTY + 8 * (pos & 3), (pos >> 2) & 1); };
#pragma unroll 1
  for (int t = 0; t < 12; t++) {
    if (t % 3 == 0) g2_released(POS_G2 + 12 + t / 3);
    const int T = t >> 1, h = t & 1;
    const uint32_t dst = sb + g3off(t), f = bars + B_F3 + 8 * t;
    mbar_expect_tx(f, h ? 48 * 224 : 64 * 224);
    if (T == 1 || T == 2) {
      const int k = 224 * c + 112 * (T - 1) + 64 * h;
      tma2d(dst, h ? &mp.wo64h : &mp.wo, f, 112 * p, k);
      tma2d(dst + 8192, h ? &mp.wo48h : &mp.wo48, f, 112 * p + 64, k);
    } else {
      const int jt = c + 2 * ((p + (T == 0 ? 0 : T - 2)) & 3);
      tma2d(dst, h ? &mp.wout64h : &mp.wout, f, 112 * p, 112 * jt + 64 * h);
      tma2d(dst + 8192, h ? &mp.wout48h : &mp.wout48, f, 112 * p + 64, 112 * jt + 64 * h);
    }
  }
#pragma unroll 1
  for (int q = 1; q < 4; q++) {
    flag_wait(FL_U + i * 8 + c + 2 * ((p + q) & 3), 8 * e1);
    mbar_arrive(bars + B_OKU + 8 * (q - 1));
  }
}

__device__ __forceinline__ void flag_release(int idx) {
  asm volatile("fence.proxy.async.global;" ::: "memory");
  asm volatile("red.release.gpu.global.add.u32 [%0], 1;" ::"l"(g_flags + idx * 8) : "memory");
}

__device__ __forceinline__ void helper_wg(const Maps& mp, uint32_t sb, int i, int j, int w, int lane) {
  const int p = j >> 1, c = j & 1;
  const uint32_t bars = sb + BAR_OFF;
  const uint32_t xw = sb + X_OFF + w * 16384;
  const uint32_t sig = bars + B_SIG + 8 * w, fre = bars + B_FREE + 8 * w;
  mbar_wait(bars + B_EP, 0);
  const unsigned e1 = lds32(bars + B_EPVAL) + 1;
  if (lane == 0) {
    mbar_wait(sig, 0);
    tma_store2d(&mp.z, xw, 128 * i + 64 * w, 112 * j);
    bulk_commit();
    bulk_wait_read();
    mbar_arrive(fre);
    bulk_wait();
    flag_release(FL_Z2N + i * 4 + p);
    flag_wait(FL_PREP, 128 * e1);
    fence_async_global();
    mbar_wait(sig, 1);
    bulk_reduce_add_f32(g_kv + (size_t)(2 * j + w) * 2048, xw, 8192);
    bulk_commit();
    bulk_wait_read();
    mbar_arrive(fre);
    bulk_wait();
    flag_release(FL_KV + j);
    if (w == 0) {
      flag_wait(FL_KV + j, 32 * e1);
      fence_async_global();
      mbar_wait(bars + B_FREE + 8, 1);
      mbar_expect_tx(bars + B_KVIN, 16384);
      bulk_load(sb + X_OFF + 16384, g_kv + (size_t)2 * j * 2048, 16384, bars + B_KVIN);
    }
  }
  __syncwarp();
  {
    const uint32_t kvt = sb + X_OFF + 8192, raw = sb + X_OFF + 16384 + w * 8192 + lane * 16;
    mbar_wait(bars + B_KVIN, 0);
#pragma unroll 4
    for (int it = 0; it < 16; it++) {
      const uint4 v = lds128(raw + it * 512);
      const int q = it >> 2, r0 = 16 * (it & 3) + (lane >> 2);
      const uint32_t a = kvt + r0 * 128 + (((4 * w + q) ^ (r0 & 7)) << 4) + 4 * (lane & 3);
      sts32(a, pack_bf16(__uint_as_float(v.x), __uint_as_float(v.y)));
      sts32(a + 1024, pack_bf16(__uint_as_float(v.z), __uint_as_float(v.w)));
    }
    fence_async_smem();
    __syncwarp();
  }
  if (lane == 0) {
    mbar_arrive(bars + B_KVRDY);
    mbar_wait(sig, 0);
    mbar_arrive(bars + B_ODONE);
    mbar_wait(bars + B_ODONE, 0);
    mbar_expect_tx(bars + B_XF1 + 8 * w, 56 * 128 * 2);
    mbar_arrive_cluster(mapa(bars + B_RDY1 + 8 * w, c ^ 1));
    if (w == 0) {
      flag_wait(FL_O + i * 2 + c, 32 * e1);
      mbar_arrive(bars + B_OKO);
    }
    mbar_wait(sig, 1);
    tma_store2d(&mp.ost, xw + 8192, 112 * p + 56 * c, 128 * i + 64 * w);
    bulk_commit();
    bulk_wait();
  }
}

__device__ __forceinline__ void helper_misc(const Maps& mp, const Params& pr, uint32_t sb, int i, int j, int lane) {
  const uint32_t bars = sb + BAR_OFF;
  unsigned epoch = 0;
  if (lane == 0) {
    asm volatile("ld.relaxed.gpu.global.u32 %0, [%1];" : "=r"(epoch) : "l"(&g_epoch) : "memory");
    sts32(bars + B_EPVAL, epoch);
    mbar_arrive(bars + B_EP);
    prefetch_map(&mp.wp); prefetch_map(&mp.wsp); prefetch_map(&mp.z); prefetch_map(&mp.wo);
    prefetch_map(&mp.wout); prefetch_map(&mp.ost); prefetch_map(&mp.wps);
    prefetch_map(&mp.wo48); prefetch_map(&mp.wo64h); prefetch_map(&mp.wo48h); prefetch_map(&mp.wout48); prefetch_map(&mp.wout64h);
    prefetch_map(&mp.wout48h);
  }
  reinterpret_cast<float4*>(g_kv)[blockIdx.x * 64 + lane] = make_float4(0.f, 0.f, 0.f, 0.f);
  reinterpret_cast<float4*>(g_kv)[blockIdx.x * 64 + 32 + lane] = make_float4(0.f, 0.f, 0.f, 0.f);
  const uint32_t stg = sb + X_OFF + 16384;
  if (i < 14 && lane < 16) {
    const uint32_t v = __ldg(reinterpret_cast<const uint32_t*>(pr.gatew) + 16 * i + lane);
    sts32(stg + 168 * 64 + (lane >> 2) * 16 + (lane & 3) * 4, v);
  }
  fence_async_smem();
  __syncwarp();
  if (lane == 0) {
    mbar_arrive(bars + B_PREP);
    mbar_wait(bars + B_PREP, 0);
    if (i < 14) {
      tma_store2d(&mp.wps, stg, 32 * i, NP2 * j);
      bulk_commit();
      bulk_wait();
    }
    flag_release(FL_PREP);
    if (blockIdx.x == 0) {
      flag_wait(FL_PREP, 128 * (epoch + 1));
      asm volatile("st.relaxed.gpu.global.u32 [%0], %1;" ::"l"(&g_epoch), "r"(epoch + 1) : "memory");
    }
  }
}

__device__ __forceinline__ void consumer(const Params& pr, uint32_t sb, const uint8_t* smem_gen, int i, int j) {
  const int w = __shfl_sync(0xffffffffu, threadIdx.x >> 7, 0), tid = threadIdx.x & 127, lane = tid & 31;
  const int warp = __shfl_sync(0xffffffffu, tid >> 5, 0);
  const int jq = lane & 3, rq = lane >> 2;
  const int p = j >> 1, c = j & 1;
  const uint32_t bars = sb + BAR_OFF;
  const uint32_t xw = sb + X_OFF + w * 16384;
  const int wbar = 1 + w;
  auto wait_full = [&](int pos) { mbar_wait(bars + B_FULL + 8 * (pos & 3), (pos >> 2) & 1); };
  auto release = [&](int pos) { if (tid == 0) mbar_arrive(bars + B_EMPTY + 8 * (pos & 3)); };
  auto slot_a = [&](int pos) { return sb + (pos & 3) * SLOT_BYTES + w * 8192; };
  auto slot_b = [&](int pos) { return sb + (pos & 3) * SLOT_BYTES + 16384; };
  auto signal = [&]() { fence_async_smem(); __syncwarp(); if (lane == 0) mbar_arrive(bars + B_SIG + 8 * w); };
  auto wait_free = [&](int n) { mbar_wait(bars + B_FREE + 8 * w, n & 1); };
  auto cut = [&]() { mbar_wait(bars + B_EP, 0); };
  const int row0 = 128 * i + 64 * w + 16 * warp + rq;
  const int mi = lane >> 3, l8 = lane & 7;
  const int srow = 16 * warp + 8 * (mi & 1) + l8;

  const uint32_t bias2 = (uint32_t)__ldg(reinterpret_cast<const unsigned short*>(pr.bsp) + row0) |
                         ((uint32_t)__ldg(reinterpret_cast<const unsigned short*>(pr.bsp) + row0 + 8) << 16);

  const int pe = (threadIdx.x >> 5) & 1, pnt = threadIdx.x >> 6;
  uint32_t pa[2][2][4], pb[3][2][2];
  auto prep_load = [&]() {
    const uint8_t* xg = smem_gen + X_OFF;
    mbar_wait(bars + B_PIN, 0);
#pragma unroll
    for (int s = 0; s < 2; s++)
#pragma unroll
      for (int hb = 0; hb < 2; hb++) {
        const int d = 16 * s + 8 * hb + 2 * jq, k = 8 * pnt + rq;
        const bool dv = d < 28;
        const int dc = dv ? d : 0, col = 28 * pe + dc;
        const uint8_t* ba = xg + k * 128 + (((col >> 3) ^ (k & 7)) << 4) + (col & 7) * 2;
#pragma unroll
        for (int part = 0; part < 3; part++) { const uint32_t v = *reinterpret_cast<const uint32_t*>(ba + part * 4096); pb[part][s][hb] = dv ? v : 0u; }
#pragma unroll
        for (int mt = 0; mt < 2; mt++) {
          const int f0 = 16 * mt + 2 * rq;
          const bool ok = dv && f0 < 28;
          const uint8_t* wa = xg + 12288 + pe * 1568 + dc * 56 + (f0 < 28 ? f0 : 0) * 2;
          const uint32_t w0 = *reinterpret_cast<const uint32_t*>(wa), w1 = *reinterpret_cast<const uint32_t*>(wa + 56);
          pa[mt][s][2 * hb] = ok ? __byte_perm(w0, w1, 0x5410) : 0u;
          pa[mt][s][2 * hb + 1] = ok ? __byte_perm(w0, w1, 0x7632) : 0u;
        }
      }
  };
  auto prep_part = [&](int part) {
    uint32_t o[4];
#pragma unroll
    for (int mt = 0; mt < 2; mt++) {
      const int f0 = 16 * mt + 2 * rq;
      float d4[4] = {0.f, 0.f, 0.f, 0.f};
#pragma unroll
      for (int s = 0; s < 2; s++) {
        if (part < 2) mma16816(d4, pa[mt][s], pb[part][s][0], pb[part][s][1]);
        else {
          uint32_t id[4];
#pragma unroll
          for (int hb = 0; hb < 2; hb++) {
            const bool hit = f0 == 16 * s + 8 * hb + 2 * jq;
            id[2 * hb] = hit ? 0x00003f80u : 0u;
            id[2 * hb + 1] = hit ? 0x3f800000u : 0u;
          }
          mma16816(d4, id, pb[part][s][0], pb[part][s][1]);
        }
      }
      o[2 * mt] = pack_bf16(d4[0], d4[1]);
      o[2 * mt + 1] = pack_bf16(d4[2], d4[3]);
    }
    const int f = 16 * (mi >> 1) + 2 * l8 + (mi & 1);
    const int n = f >= 28 ? 175 : part < 2 ? 56 * part + 8 * (f >> 2) + 2 * (f & 3) + pe : 112 + 28 * pe + f;
    stsm4(sb + X_OFF + 16384 + n * 64 + ((pnt ^ ((n >> 1) & 3)) << 4), o[0], o[1], o[2], o[3]);
  };
  if (i < 14) {
    prep_load();

    prep_part(0); prep_part(1); prep_part(2);
    fence_async_smem();
  }
  __syncwarp();
  if (lane == 0) mbar_arrive(bars + B_PREP);


  constexpr int NZ2 = 56, Z2O = 0;
  constexpr int NZ1 = 56, Z1O = 64;
  float acc1[120];
  {
    auto p1step = [&](int m) {
      const int pos = POS_P1 + m;
      wait_full(pos);
      const uint32_t a = slot_a(pos), b = slot_b(pos);
      fence_acc(acc1);
      wg_fence();
#pragma unroll
      for (int k = 0; k < 4; k++) wgmma_ss_n240<0, 1>(acc1, desc128(a + 32 * k, 16), desc128(b + 2048 * k, 8192), (m | k) != 0);
      wg_commit();
      if (m > 0) { wg_wait<1>(); release(pos - 1); }
    };
#pragma unroll 1
    for (int m = 0; m < 7; m++) p1step(m);
    wg_wait<0>();
    fence_acc(acc1);
    release(POS_P1 + 6);
  }
  mbar_wait(bars + B_EP, 0);
  const unsigned e1 = lds32(bars + B_EPVAL) + 1;

  uint32_t z1p[NZ1 / 2];
  float z2v[NZ2];
#pragma unroll
  for (int t = 0; t < NZ1; t += 2) z1p[t >> 1] = pack_bf16(acc1[Z1O + t], acc1[Z1O + t + 1]);
  pin_regs(z1p);
#pragma unroll
  for (int t = 0; t < NZ2; t++) z2v[t] = acc1[Z2O + t];
  float st_s[2] = {0.f, 0.f}, st_q[2] = {0.f, 0.f};
  auto gelu_z2 = [&](int t0, int t1) {
#pragma unroll
    for (int t = 0; t < NZ2; t++)
      if (t >= t0 && t < t1) {
        const float y = gelu_tanh(z2v[t]);
        z2v[t] = y;
        st_s[(t >> 1) & 1] += y;
        st_q[(t >> 1) & 1] = fmaf(y, y, st_q[(t >> 1) & 1]);
      }
    fence_acc(z2v);
  };
  auto post_stats = [&]() {
#pragma unroll
    for (int r = 0; r < 2; r++) {
      st_s[r] += __shfl_xor_sync(0xffffffffu, st_s[r], 1); st_q[r] += __shfl_xor_sync(0xffffffffu, st_q[r], 1);
      st_s[r] += __shfl_xor_sync(0xffffffffu, st_s[r], 2); st_q[r] += __shfl_xor_sync(0xffffffffu, st_q[r], 2);
    }
    if (jq < 2) {
      const float s = jq == 0 ? st_s[0] : st_s[1], q = jq == 0 ? st_q[0] : st_q[1];
      const unsigned long long v = ((unsigned long long)__float_as_uint(q) << 32) | ((__float_as_uint(s) & ~3u) | (e1 & 3u));
      asm volatile("st.relaxed.gpu.global.b64 [%0], %1;" ::"l"(g_stats + (i * 8 + j) * 128 + 64 * w + 16 * warp + 8 * jq + rq), "l"(v) : "memory");
    }
  };
  auto gelu_z1 = [&](int t0, int t1) {
#pragma unroll
    for (int t = 0; t < NZ1 / 2; t++)
      if (t >= t0 && t < t1) {
        z1p[t] = pack_bf16(gelu_tanh(bf_lo(z1p[t])), gelu_tanh(bf_hi(z1p[t])));
        asm volatile("" : "+r"(z1p[t]));
      }
  };
  auto layernorm_store = [&]() {
    unsigned long long v[4];
    poll_stats(g_stats + (i * 8 + 2 * jq) * 128 + 64 * w + 16 * warp + rq, e1, v);
    float mean_r[2], rstd[2];
#pragma unroll
    for (int r = 0; r < 2; r++) {
      float s = __uint_as_float((uint32_t)v[2 * r] & ~3u) + __uint_as_float((uint32_t)v[2 * r + 1] & ~3u);
      float q = __uint_as_float((uint32_t)(v[2 * r] >> 32)) + __uint_as_float((uint32_t)(v[2 * r + 1] >> 32));
      s += __shfl_xor_sync(0xffffffffu, s, 1); q += __shfl_xor_sync(0xffffffffu, q, 1);
      s += __shfl_xor_sync(0xffffffffu, s, 2); q += __shfl_xor_sync(0xffffffffu, q, 2);
      const float mean = s * (1.f / FH);
      const float var = fmaxf(fmaf(-mean, mean, q * (1.f / FH)), 0.f);
      rstd[r] = rsqrtf(var + 1e-5f);
      mean_r[r] = -mean * rstd[r];
    }
#pragma unroll
    for (int g = 0; g < NZ2 / 4; g += 2) {
      uint32_t u[4];
#pragma unroll
      for (int q = 0; q < 4; q++) {
        const int t = 4 * (g + (q >> 1)) + 2 * (q & 1), r = q & 1;
        u[q] = pack_bf16(fmaf(z2v[t], rstd[r], mean_r[r]), fmaf(z2v[t + 1], rstd[r], mean_r[r]));
      }
      const int f = 8 * (g + (mi >> 1)) + l8, ch = 2 * warp + (mi & 1);
      stsm4t(xw + f * 128 + ((ch ^ l8) << 4), u[0], u[1], u[2], u[3]);
    }
    signal();
  };

  uint32_t pqk[28];
  float gate0, gate1;
  auto vt_addr = [&](int t) { return sb + (2 * w + (t >> 5)) * SLOT_BYTES + SPARE_OFF + (t & 31) * 128; };
  {
    float acc2[NP2 / 2];
    auto p2issue = [&](int m) {
      const int pos = POS_P2 + m;
      wait_full(pos);
      const uint32_t a = slot_a(pos), b = slot_b(pos);
      fence_acc(acc2);
      wg_fence();
#pragma unroll
      for (int k = 0; k < 4; k++) wgmma_ss_n176<0, 0>(acc2, desc128(a + 32 * k, 16), desc128(b + 32 * k, 16), (m | k) != 0);
      wg_commit();
      if (m > 0) { wg_wait<1>(); release(pos - 1); }
    };
    p2issue(0); cut(); gelu_z2(0, 56); post_stats();
    p2issue(1);
    p2issue(2);
    p2issue(3); cut(); layernorm_store();

#pragma unroll 1
    for (int m = 4; m < 7; m++) p2issue(m);
    wg_wait<0>();
    fence_acc(acc2);
    release(POS_P2 + 6);
#pragma unroll
    for (int t = 0; t < 28; t++) { pqk[t] = pack_bf16(acc2[2 * t], acc2[2 * t + 1]); }
    pin_regs(pqk);
    gate0 = __shfl_sync(0xffffffffu, acc2[84], lane & ~3);
    gate1 = __shfl_sync(0xffffffffu, acc2[86], lane & ~3);
    gate0 = __fdividef(1.f, 1.f + __expf(-gate0));
    gate1 = __fdividef(1.f, 1.f + __expf(-gate1));
    uint32_t vv[8][2];
#pragma unroll
    for (int r = 0; r < 2; r++) {
      auto pk = [&](int g) { return pack_bf16(acc2[4 * g + 2 * r], acc2[4 * g + 2 * r + 1]); };
      vv[0][r] = pk(14); vv[1][r] = pk(15); vv[2][r] = pk(16);
      const uint32_t mid = pk(17);
      vv[3][r] = jq < 2 ? mid : (jq == 2 ? 0x3f80u : 0u);
      vv[4][r] = jq >= 2 ? mid : (jq == 0 ? 0x3f80u : 0u);
      vv[5][r] = pk(18); vv[6][r] = pk(19); vv[7][r] = pk(20);
    }
    const uint32_t vrow = vt_addr(srow);
#pragma unroll
    for (int g = 0; g < 8; g += 2) {
      const int ch = g + (mi >> 1);
      stsm4(vrow + ((ch ^ l8) << 4), vv[g][0], vv[g][1], vv[g + 1][0], vv[g + 1][1]);
    }
  }

  uint32_t phiq[2][4][4];
  float kv0[16];
  auto fmap = [&](int base, int e, int r, uint32_t (&o)[8]) {
    float v[7];
#pragma unroll
    for (int g = 0; g < 7; g++) { const uint32_t x = pqk[2 * (base + g) + r]; v[g] = e == 0 ? bf_lo(x) : bf_hi(x); }
    feature_map(v, o);
  };
  uint32_t fk0[8];
  auto phi_k_row = [&](int e, int r) {
    if (r == 0) { fmap(7, e, 0, fk0); pin_regs(fk0); return; }
    uint32_t fk1[8];
    fmap(7, e, 1, fk1);
#pragma unroll
    for (int s = 0; s < 4; s++) {
      const int ch = 2 * s + (mi >> 1);
      stsm4(xw + 8192 * e + srow * 128 + ((ch ^ l8) << 4), fk0[2 * s], fk1[2 * s], fk0[2 * s + 1], fk1[2 * s + 1]);
    }
  };
  auto kv_issue = [&]() {
    fence_async_smem();
    bar_sync(3, 256);
    wg_fence();
#pragma unroll
    for (int s = 0; s < 8; s++) {
      const uint32_t a = sb + X_OFF + (s >> 2) * 16384 + w * 8192 + (s & 3) * 2048;
      const uint32_t b = sb + (2 * (s >> 2) + ((s >> 1) & 1)) * SLOT_BYTES + SPARE_OFF + (s & 1) * 2048 + 64 * w;
      wgmma_ss_n32<1, 1>(kv0, desc128(a, 16), desc128(b, 16), s != 0);
    }
    wg_commit();
  };
  auto kv_flush = [&]() {
    fence_acc(kv0);
    bar_sync(3, 256);
#pragma unroll
    for (int q = 0; q < 4; q++)
      sts128(xw + q * 2048 + tid * 16, __float_as_uint(kv0[4 * q]), __float_as_uint(kv0[4 * q + 1]), __float_as_uint(kv0[4 * q + 2]), __float_as_uint(kv0[4 * q + 3]));
    signal();
  };
  auto phi_q_row = [&](int e, int r) {
    uint32_t fq[8];
    fmap(0, e, r, fq);
#pragma unroll
    for (int s = 0; s < 4; s++) {
      phiq[e][s][r] = fq[2 * s]; phiq[e][s][2 + r] = fq[2 * s + 1];
      asm volatile("" : "+r"(phiq[e][s][r]), "+r"(phiq[e][s][2 + r]));
    }
  };
  float oa[16];
  uint32_t ov[7][2];
  auto o_issue = [&](int e) {
    const uint32_t kvt = sb + X_OFF + 8192 + 64 * e;
    wg_fence();
#pragma unroll
    for (int s = 0; s < 4; s++) wgmma_rs_n32<1>(oa, phiq[e][s][0], phiq[e][s][1], phiq[e][s][2], phiq[e][s][3], desc128(kvt + 2048 * s, 16), s != 0);
    wg_commit();
  };
  auto o_finish = [&](int e) {
    fence_acc(oa);
#pragma unroll
    for (int s = 0; s < 4; s++) pin_regs(phiq[e][s]);
#pragma unroll
    for (int r = 0; r < 2; r++) {
      const float gt = r == 0 ? gate0 : gate1;
      const float den = e == 0 ? __shfl_sync(0xffffffffu, oa[12 + 2 * r], (lane & ~3) | 2) : __shfl_sync(0xffffffffu, oa[2 * r], lane & ~3);
      const float sc = __fdividef(gt, den + 1e-6f);
      if (e == 0) {
#pragma unroll
        for (int g = 0; g < 4; g++) ov[g][r] = pack_bf16(oa[4 * g + 2 * r] * sc, oa[4 * g + 2 * r + 1] * sc);
      } else {
        const uint32_t mid = pack_bf16(oa[2 * r] * sc, oa[2 * r + 1] * sc);
        ov[3][r] = jq < 2 ? ov[3][r] : mid;
#pragma unroll
        for (int g = 0; g < 3; g++) ov[4 + g][r] = pack_bf16(oa[4 * (g + 1) + 2 * r] * sc, oa[4 * (g + 1) + 2 * r + 1] * sc);
      }
    }
  };
  auto o_store = [&]() {
    uint2* dst = g_O + (size_t)((i * 8 + j) * 2 + w) * 7 * 128 + tid;
#pragma unroll
    for (int g = 0; g < 7; g++) st_unit8(dst + g * 128, tag_lo(ov[g][0], e1), ov[g][1]);
    __syncwarp();
    if (lane == 0) {
      asm volatile("red.relaxed.gpu.global.add.u32 [%0], 1;" ::"l"(g_flags + (FL_O + i * 2 + (j >> 2)) * 8) : "memory");
      mbar_arrive(bars + B_SIG + 8 * w);
    }
  };

  {
    float acc[112];
    auto g2issue = [&](int m, bool first) {
      const int pos = POS_G2 + m;
      wait_full(pos);
      const uint32_t a = slot_a(pos), b = slot_b(pos);
      fence_acc(acc);
      wg_fence();
#pragma unroll
      for (int k = 0; k < 4; k++) wgmma_ss_n224<0, 0>(acc, desc128(a + 32 * k, 16), desc128(b + 32 * k, 16), (m | k) != 0);
      wg_commit();
      wg_wait<1>();
      if (!first) release(pos - 1);
    };
    wait_free(0);
    phi_k_row(0, 0); phi_k_row(0, 1);
    phi_k_row(1, 0); phi_k_row(1, 1);
    kv_issue();
    g2issue(0, true); cut(); kv_flush();
    g2issue(1, false); cut(); phi_q_row(0, 0);
    g2issue(2, false); cut(); phi_q_row(0, 1);
    g2issue(3, false); cut(); phi_q_row(1, 0);
    g2issue(4, false); cut(); phi_q_row(1, 1);
    g2issue(5, false); cut(); gelu_z1(0, 7);
    g2issue(6, false); cut(); gelu_z1(7, 14);
    g2issue(7, false); cut(); gelu_z1(14, 21);
    g2issue(8, false); cut(); gelu_z1(21, 28);
#pragma unroll 1
    for (int m = 9; m <= OSTEP; m++) g2issue(m, false);
    mbar_wait(bars + B_KVRDY, 0);
    o_issue(0);
    g2issue(OSTEP + 1, false); cut(); o_finish(0); o_issue(1);
    g2issue(OSTEP + 2, false); cut(); o_finish(1); o_store();
#pragma unroll 1
    for (int m = OSTEP + 3; m < 16; m++) g2issue(m, false);
    wg_wait<0>();
    fence_acc(acc);
    release(POS_G2 + 15);
    const uint32_t peer = c ^ 1;
    mbar_wait(bars + B_RDY1 + 8 * w, 0);
    {
      const uint32_t rdst = mapa(xw + tid * 16, peer), rbar = mapa(bars + B_XF1 + 8 * w, peer);
#pragma unroll
      for (int t = 0; t < 56; t += 8)
        st_async4u(rdst + t * 256, pack_bf16(acc[56 + t], acc[56 + t + 1]), pack_bf16(acc[56 + t + 2], acc[56 + t + 3]),
                   pack_bf16(acc[56 + t + 4], acc[56 + t + 5]), pack_bf16(acc[56 + t + 6], acc[56 + t + 7]), rbar);
    }

    const uint2* osrc = g_O + (size_t)((i * 8 + 4 * c) * 2 + w) * 7 * 128 + tid;
    auto usrc = [&](int q) { return g_U + (size_t)((i * 8 + c + 2 * ((p + q) & 3)) * 2 + w) * 7 * 128 + tid; };
    uint32_t ra[28], rb[28], rc[28];
    mbar_wait(bars + B_OKO, 0);
    o_load(osrc, osrc + 1792, ra);
    float acc3[56];
    uint32_t up[28];
    {
      const float bias[2] = {bf_lo(bias2), bf_hi(bias2)};
      const float og[2] = {1.f - gate0, 1.f - gate1};
      mbar_wait(bars + B_XF1 + 8 * w, 0);
#pragma unroll
      for (int t = 0; t < 56; t += 8) {
        const uint4 v = lds128(xw + tid * 16 + t * 256);
        const uint32_t vv[4] = {v.x, v.y, v.z, v.w};
#pragma unroll
        for (int q = 0; q < 4; q++) {
          const int a = t + 2 * q, r = q & 1;
          const float g0 = acc[a] + bf_lo(vv[q]) + bias[r], g1 = acc[a + 1] + bf_hi(vv[q]) + bias[r];
          const uint32_t z = z1p[a >> 1];
          up[a >> 1] = pack_bf16(bf_lo(z) * g0 * og[r], bf_hi(z) * g1 * og[r]);
        }
      }
      uint4* dst = g_U + (size_t)((i * 8 + j) * 2 + w) * 7 * 128 + tid;
#pragma unroll
      for (int q = 0; q < 7; q++) st_unit16(dst + q * 128, tag_lo(up[4 * q], e1), up[4 * q + 1], up[4 * q + 2], up[4 * q + 3]);
      __syncwarp();
      if (lane == 0) asm volatile("red.relaxed.gpu.global.add.u32 [%0], 1;" ::"l"(g_flags + (FL_U + i * 8 + j) * 8) : "memory");
    }
    auto g3tile = [&](int T, uint32_t (&v)[28]) {
      mbar_wait(bars + B_F3 + 8 * (2 * T), 0);
      mbar_wait(bars + B_F3 + 8 * (2 * T + 1), 0);
      const uint32_t b0 = sb + g3off(2 * T), b1 = sb + g3off(2 * T + 1);
      fence_acc(acc3);
      wg_fence();
#pragma unroll
      for (int s = 0; s < 7; s++)
        wgmma_rs_n112<1>(acc3, v[4 * s], v[4 * s + 1], v[4 * s + 2], v[4 * s + 3],
                         desc128((s < 4 ? b0 + 2048 * s : b1 + 2048 * (s - 4)), 8192), T != 0 || s != 0);
      wg_commit();
    };
    auto o_verify = [&](const uint2* p0, const uint2* p1, uint32_t (&v)[28]) {
      uint32_t bad = 0;
#pragma unroll
      for (int t = 0; t < 14; t++) bad |= v[2 * t] ^ e1;
      if (__any_sync(0xffffffffu, bad & 1)) { o_poll(p0, p1, e1); o_load(p0, p1, v); }
    };
    g3tile(0, up);
    o_load(osrc + 3584, osrc + 5376, rb);
    bar_sync(wbar, 128);
    if (tid == 0) {
      mbar_expect_tx(bars + B_XF2 + 8 * w, 16 * 128 * 4);
      mbar_arrive_cluster(mapa(bars + B_RDY2 + 8 * w, peer));
    }
    o_verify(osrc, osrc + 1792, ra);
    g3tile(1, ra);
    auto u_fetch = [&](int q, uint32_t (&v)[28]) { mbar_wait(bars + B_OKU + 8 * (q - 1), 0); u_load(usrc(q), v); };
    auto u_verify = [&](int q, uint32_t (&v)[28]) {
      uint32_t bad = 0;
#pragma unroll
      for (int t = 0; t < 7; t++) bad |= v[4 * t] ^ e1;
      if (__any_sync(0xffffffffu, bad & 1)) { u_poll(usrc(q), e1); u_load(usrc(q), v); }
    };
    wg_wait<1>();
    pin_regs(up);
    u_fetch(1, rc);
    o_verify(osrc + 3584, osrc + 5376, rb);
    g3tile(2, rb);
    wg_wait<1>();
    pin_regs(ra);
    u_fetch(2, ra);
    u_verify(1, rc);
    g3tile(3, rc);
    wg_wait<1>();
    pin_regs(rb);
    u_fetch(3, rb);
    u_verify(2, ra);
    g3tile(4, ra);
    u_verify(3, rb);
    g3tile(5, rb);
    wg_wait<0>();
    fence_acc(acc3);
    pin_regs(ra); pin_regs(rb); pin_regs(rc);
    float keep[28];
#pragma unroll
    for (int t = 0; t < 28; t++) { const float lo = acc3[t], hi = acc3[28 + t]; keep[t] = c ? hi : lo; acc3[t] = c ? lo : hi; }
    const uint32_t xbuf = xw + tid * 16;
    mbar_wait(bars + B_RDY2 + 8 * w, 0);
    {
      const uint32_t rdst = mapa(xbuf, peer), rbar = mapa(bars + B_XF2 + 8 * w, peer);
      uint32_t sv[16];
#pragma unroll
      for (int t = 0; t < 14; t++) sv[t] = pack_bf16(acc3[2 * t], acc3[2 * t + 1]);
      sv[14] = 0; sv[15] = 0;
#pragma unroll
      for (int t = 0; t < 4; t++) st_async4u(rdst + t * 2048, sv[4 * t], sv[4 * t + 1], sv[4 * t + 2], sv[4 * t + 3], rbar);
    }
    mbar_wait(bars + B_XF2 + 8 * w, 0);
    uint32_t ov2[14];
#pragma unroll
    for (int t = 0; t < 4; t++) {
      const uint4 v = lds128(xbuf + t * 2048);
      const uint32_t vv[4] = {v.x, v.y, v.z, v.w};
#pragma unroll
      for (int q = 0; q < 4; q++)
        if (4 * t + q < 14) ov2[4 * t + q] = pack_bf16(keep[2 * (4 * t + q)] + bf_lo(vv[q]), keep[2 * (4 * t + q) + 1] + bf_hi(vv[q]));
    }
#pragma unroll
    for (int g = 0; g < 6; g += 2) stsm4(xw + 8192 + srow * 112 + ((g + (mi >> 1)) << 4), ov2[2 * g], ov2[2 * g + 1], ov2[2 * g + 2], ov2[2 * g + 3]);
    stsm2(xw + 8192 + srow * 112 + 96, ov2[12], ov2[13]);
    signal();
  }
}

__global__ void __launch_bounds__(NTHREADS, 1)
fused_kernel(const __grid_constant__ Maps mp, const Params pr) {
  extern __shared__ uint8_t smem_raw[];
  const uint32_t sb = (smem_u32(smem_raw) + 1023) & ~1023u;
  const uint32_t bars = sb + BAR_OFF;
  const int i = blockIdx.x >> 3, j = blockIdx.x & 7;
  if ((threadIdx.x >> 5) == 8) {
    if (elect_one()) {
#pragma unroll
      for (int s = 0; s < 4; s++) { mbar_init(bars + B_FULL + 8 * s, 1); mbar_init(bars + B_EMPTY + 8 * s, 2); }
#pragma unroll
      for (int s = 0; s < 2; s++) {
        mbar_init(bars + B_RDY1 + 8 * s, 1); mbar_init(bars + B_RDY2 + 8 * s, 1);
        mbar_init(bars + B_SIG + 8 * s, 4); mbar_init(bars + B_FREE + 8 * s, 1);
        mbar_init(bars + B_XF1 + 8 * s, 1); mbar_init(bars + B_XF2 + 8 * s, 1);
      }
      mbar_init(bars + B_KVRDY, 2);
      mbar_init(bars + B_PREP, 9);
      mbar_init(bars + B_PIN, 1);
      mbar_init(bars + B_KVIN, 1);
      mbar_init(bars + B_ODONE, 2);
      mbar_init(bars + B_EP, 1);
      asm volatile("fence.mbarrier_init.release.cluster;" ::: "memory");
      asm volatile("fence.proxy.async.shared::cta;" ::: "memory");
      if (i < 14) {
        mbar_expect_tx(bars + B_PIN, 3 * 4096 + 3136);
#pragma unroll
        for (int part = 0; part < 3; part++) tma2d(sb + X_OFF + part * 4096, &mp.wq, bars + B_PIN, part * DM + 56 * j, 32 * i);
        bulk_load(sb + X_OFF + 12288, pr.wphi + 1568 * j, 3136, bars + B_PIN);
      }
      issue_p1(mp, sb, 0, i, j);
    }
    __syncwarp();
  }
  __syncthreads();
  asm volatile("barrier.cluster.arrive.relaxed.aligned;" ::: "memory");
  if (threadIdx.x >= 256) {
    asm volatile("setmaxnreg.dec.sync.aligned.u32 40;");
    const int warp = threadIdx.x >> 5, lane = threadIdx.x & 31;
    if (warp == 8) {
      if (elect_one()) {
#pragma unroll 1
        for (int m = 1; m < 4; m++) issue_p1(mp, sb, m, i, j);
#pragma unroll
        for (int s = 0; s < 12; s++) mbar_init(bars + B_F3 + 8 * s, 1);
        mbar_init(bars + B_OKO, 1);
        mbar_init(bars + B_OKU, 1); mbar_init(bars + B_OKU + 8, 1); mbar_init(bars + B_OKU + 16, 1);
        asm volatile("fence.proxy.async.shared::cta;" ::: "memory");
      }
      __syncwarp();
      asm volatile("barrier.cluster.wait.aligned;" ::: "memory");
      if (elect_one()) producer(mp, sb, i, j);
    } else if (warp == 11) {
      helper_misc(mp, pr, sb, i, j, lane);
    } else {
      helper_wg(mp, sb, i, j, warp - 9, lane);
    }
  } else {
    asm volatile("setmaxnreg.inc.sync.aligned.u32 232;");
    asm volatile("barrier.cluster.wait.aligned;" ::: "memory");
    consumer(pr, sb, smem_raw + (sb - smem_u32(smem_raw)), i, j);
  }
}

typedef CUresult (*EncodeFn)(CUtensorMap*, CUtensorMapDataType, cuuint32_t, void*, const cuuint64_t*, const cuuint64_t*,
                             const cuuint32_t*, const cuuint32_t*, CUtensorMapInterleave, CUtensorMapSwizzle,
                             CUtensorMapL2promotion, CUtensorMapFloatOOBfill);

void make_map(EncodeFn fn, CUtensorMap* m, const void* ptr, uint64_t cols, uint64_t rows, uint32_t box_cols, uint32_t box_rows,
              CUtensorMapSwizzle sw = CU_TENSOR_MAP_SWIZZLE_128B) {
  cuuint64_t dims[2] = {cols, rows};
  cuuint64_t strides[1] = {cols * 2};
  cuuint32_t box[2] = {box_cols, box_rows};
  cuuint32_t es[2] = {1, 1};
  fn(m, CU_TENSOR_MAP_DATA_TYPE_BFLOAT16, 2, const_cast<void*>(ptr), dims, strides, box, es, CU_TENSOR_MAP_INTERLEAVE_NONE,
     sw, CU_TENSOR_MAP_L2_PROMOTION_L2_128B, CU_TENSOR_MAP_FLOAT_OOB_FILL_NONE);
}

}

extern "C" void kernel_launch(void* const* d_in, const int* in_sizes, int n_in, void* d_out, int out_size) {
  (void)in_sizes; (void)n_in; (void)out_size;
  static Maps mp;
  static const void* cached[11] = {};
  static bool init = false;
  bool same = init && cached[10] == d_out;
  for (int t = 0; t < 10; t++) same = same && cached[t] == d_in[t];
  if (!same) {
    static EncodeFn fn = nullptr;
    if (!fn) {
      void* f = nullptr;
      cudaDriverEntryPointQueryResult st;
      cudaGetDriverEntryPoint("cuTensorMapEncodeTiled", &f, cudaEnableDefault, &st);
      fn = (EncodeFn)f;
      cudaFuncSetAttribute(fused_kernel, cudaFuncAttributeMaxDynamicSharedMemorySize, SMEM_BYTES);
    }
    void *wp, *z;
    cudaGetSymbolAddress(&wp, g_Wp);
    cudaGetSymbolAddress(&z, g_z2nT);
    make_map(fn, &mp.x, d_in[0], DM, SEQ, 64, 128);
    make_map(fn, &mp.win, d_in[5], 2 * FH, DM, 64, 64);
    make_map(fn, &mp.wp, wp, DM, 8 * NP2, 64, 169);
    make_map(fn, &mp.wq, d_in[1], KALL, DM, 64, 32);
    make_map(fn, &mp.wsp, d_in[6], SEQ, SEQ, 64, 128);
    make_map(fn, &mp.z, z, SEQ, FH, 64, 112);
    make_map(fn, &mp.wps, wp, DM, 8 * NP2, 32, NP2, CU_TENSOR_MAP_SWIZZLE_64B);
    make_map(fn, &mp.wo, d_in[3], DM, DM, 64, 64);
    make_map(fn, &mp.wout, d_in[8], DM, FH, 64, 64);
    make_map(fn, &mp.win48, d_in[5], 2 * FH, DM, 48, 64);
    make_map(fn, &mp.wo48, d_in[3], DM, DM, 48, 64);
    make_map(fn, &mp.wo64h, d_in[3], DM, DM, 64, 48);
    make_map(fn, &mp.wo48h, d_in[3], DM, DM, 48, 48);
    make_map(fn, &mp.wout48, d_in[8], DM, FH, 48, 64);
    make_map(fn, &mp.wout64h, d_in[8], DM, FH, 64, 48);
    make_map(fn, &mp.wout48h, d_in[8], DM, FH, 48, 48);
    make_map(fn, &mp.ost, d_out, DM, SEQ, 56, 64, CU_TENSOR_MAP_SWIZZLE_NONE);
    for (int t = 0; t < 10; t++) cached[t] = d_in[t];
    cached[10] = d_out;
    init = true;
  }
  Params pr;
  pr.wphi = (const __nv_bfloat16*)d_in[2];
  pr.bsp = (const __nv_bfloat16*)d_in[7];
  pr.gatew = (const __nv_bfloat16*)d_in[9];
  cudaLaunchConfig_t cfg = {};
  cfg.gridDim = dim3(128);
  cfg.blockDim = dim3(NTHREADS);
  cfg.dynamicSmemBytes = SMEM_BYTES;
  cfg.stream = cudaStreamPerThread;
  cudaLaunchAttribute at[1];
  at[0].id = cudaLaunchAttributeClusterDimension;
  at[0].val.clusterDim.x = 2;
  at[0].val.clusterDim.y = 1;
  at[0].val.clusterDim.z = 1;
  cfg.attrs = at;
  cfg.numAttrs = 1;
  cudaLaunchKernelEx(&cfg, fused_kernel, mp, pr);
}
```
